```python
import torch

def _softmax(x, axis=-1):
    return torch.softmax(x, dim=axis)
def _gelu(x):
    return torch.nn.functional.gelu(x, approximate="tanh")
def _silu(x):
    return torch.nn.functional.silu(x)
def _sigmoid(x):
    return torch.sigmoid(x)
def _layernorm(x, axis=-1, eps=1e-5):
    m = x.mean(dim=axis, keepdim=True)
    v = x.var(dim=axis, keepdim=True, unbiased=False)
    return (x - m) / torch.sqrt(v + eps)
def _scatter_add(tgt, idx, src, axis=0):
    return tgt.clone().index_add_(axis, idx, src)
def _segment_sum(src, seg, n):
    out = torch.zeros((n,) + src.shape[1:], dtype=src.dtype)
    return out.index_add_(0, seg, src)
def _pad(x, pw):
    flat = tuple(v for pair in reversed(pw) for v in pair)
    return torch.nn.functional.pad(x, flat)

kernel_name = 'gated_mix__ssm_conv_s4d__glu_gated_bilinear__prompt'

def setup_inputs():

    _w = (lambda a: (lambda t: t.to(torch.bfloat16) if t.is_floating_point() else t)(torch.as_tensor(a)))
    def _A_setup():
        Bsz, L, D, N = 1, 2048, 512, 128
        return {
            "u": _w((lambda *s: torch.randn(*s, dtype=torch.bfloat16) * 0.05)(Bsz, L, D)),
            "log_A_real": _w((lambda *s: torch.randn(*s, dtype=torch.bfloat16) * 3.2)(D, N) * 0.5),
            "A_imag": _w((lambda *s: torch.randn(*s, dtype=torch.bfloat16) * 0.05)(D, N) * 3.14),
            "C_real": _w((lambda *s: torch.randn(*s, dtype=torch.bfloat16) * 0.05)(D, N) / N ** 0.5),
            "C_imag": _w((lambda *s: torch.randn(*s, dtype=torch.bfloat16) * 0.1)(D, N) / N ** 0.5),
            "log_dt": _w((lambda *s: torch.randn(*s, dtype=torch.bfloat16) * 0.05)(D) * 0.5 - 4.0),
            "D_skip": _w((lambda *s: torch.randn(*s, dtype=torch.bfloat16) * 0.05)(D)),
        }
    _A_in = _A_setup()

    def _B_setup():
        B, S, D, F = 1, 2048, 512, 1792
        return {
            "x": _w((lambda *s: torch.randn(*s, dtype=torch.bfloat16) * 0.05)(B, S, D)),
            "w_gate": _w((lambda *s: torch.randn(*s, dtype=torch.bfloat16) * 0.8)(D, F) * (D ** -0.5)),
            "w_up": _w((lambda *s: torch.randn(*s, dtype=torch.bfloat16) * 0.8)(D, F) * (D ** -0.5)),
            "w_down": _w((lambda *s: torch.randn(*s, dtype=torch.bfloat16) * 0.8)(F, D) * (F ** -0.5)),
        }
    _B_in = _B_setup()

    return {
        "A_u": _A_in["u"],
        "A_log_A_real": _A_in["log_A_real"],
        "A_A_imag": _A_in["A_imag"],
        "A_C_real": _A_in["C_real"],
        "A_C_imag": _A_in["C_imag"],
        "A_log_dt": _A_in["log_dt"],
        "A_D_skip": _A_in["D_skip"],
        "B_x": _B_in["x"],
        "B_w_gate": _B_in["w_gate"],
        "B_w_up": _B_in["w_up"],
        "B_w_down": _B_in["w_down"],
        "gate_w": _w((lambda *s: torch.randn(*s, dtype=torch.bfloat16) * 0.05)(512) * 16.0),
    }

def reference(A_u, A_log_A_real, A_A_imag, A_C_real, A_C_imag, A_log_dt, A_D_skip, B_x, B_w_gate, B_w_up, B_w_down, gate_w):
    def _A_ref(u, log_A_real, A_imag, C_real, C_imag, log_dt, D_skip):
        L = u.shape[1]
        dt = torch.exp(log_dt)
        A = -torch.exp(log_A_real) + 1j * A_imag
        C = (C_real + 1j * C_imag) * dt[:, None]
        pos = (lambda x, dt: x.to(dt))(torch.arange(L), log_dt.dtype)
        P = torch.exp((A * dt[:, None])[:, :, None] * pos[None, None, :])
        K = 2.0 * torch.einsum("dn,dnl->dl", C, P).real
        L2 = 2 * L
        u_t = (lambda x, *d: x.permute(*d))(u, 0, 2, 1)
        Kf = (lambda x, *a, **k: torch.fft.rfft(x.float(), *a, **k))(K, L2)
        Uf = (lambda x, *a, **k: torch.fft.rfft(x.float(), *a, **k))(u_t, L2)
        y = (lambda x, *a, **k: torch.fft.irfft(x, *a, **k).to(torch.bfloat16))(Uf * Kf[None, :, :], L2)[:, :, :L]
        y = (lambda x, *d: x.permute(*d))(y, 0, 2, 1)
        return y + u * D_skip[None, None, :]

    def _B_ref(x, w_gate, w_up, w_down):
        g = torch.einsum("bsd,df->bsf", x, w_gate)
        u = torch.einsum("bsd,df->bsf", x, w_up)
        h = g * u
        return torch.einsum("bsf,fd->bsd", h, w_down)

    x = A_u
    g = _sigmoid((x * gate_w).sum(-1, keepdims=True))
    a = _A_ref(x, A_log_A_real, A_A_imag, A_C_real, A_C_imag, A_log_dt, A_D_skip)
    b = _B_ref(x, B_w_gate, B_w_up, B_w_down)
    return g * a + (1 - g) * b
```

```cpp
#include <cuda_runtime.h>
#include <cuda_bf16.h>
#include <cuda_fp16.h>
#include <cuda.h>
#include <stdint.h>

namespace {

constexpr int L_ = 2048, D_ = 512, NS_ = 128, F_ = 1792;

__device__ __align__(1024) __nv_bfloat16 g_h[(size_t)L_ * F_];
__device__ __align__(1024) __nv_bfloat16 g_a[(size_t)D_ * L_];
__device__ __align__(1024) __nv_bfloat16 g_ut[(size_t)D_ * L_];
__device__ __align__(1024) uint32_t g_gate[L_];
__device__ __align__(1024) unsigned g_flags[45 * 32];
constexpr int FL_H1 = 0, FL_H2 = 16, FL_DONE = 32, FL_UT = 33, FL_CONV = 41, FL_N = 45;


__device__ __forceinline__ uint32_t smem_u32(const void* p) { return (uint32_t)__cvta_generic_to_shared(p); }
__device__ __forceinline__ void mbar_init(uint32_t b, int c) { asm volatile("mbarrier.init.shared::cta.b64 [%0], %1;" ::"r"(b), "r"(c)); }
#define PRED_BEGIN(n) "{\n.reg .pred q;\nsetp.ne.u32 q, %" #n ", 0;\n"
__device__ __forceinline__ void mbar_expect_tx(uint32_t pr, uint32_t b, uint32_t bytes) {
  asm volatile(PRED_BEGIN(2) "@q mbarrier.arrive.expect_tx.shared::cta.b64 _, [%0], %1;\n}" ::"r"(b), "r"(bytes), "r"(pr) : "memory");
}
__device__ __forceinline__ void mbar_wait(uint32_t b, uint32_t ph) {
  asm volatile("{\n.reg .pred p;\nWL: mbarrier.try_wait.parity.shared::cta.b64 p, [%0], %1, 0x989680;\n@p bra WD;\nbra WL;\nWD:\n}" ::"r"(b), "r"(ph) : "memory");
}
__device__ __forceinline__ void mbar_arrive_cta(uint32_t pr, uint32_t b, uint32_t cta) {
  asm volatile(PRED_BEGIN(2) ".reg .b32 ra;\nmapa.shared::cluster.u32 ra, %0, %1;\n@q mbarrier.arrive.shared::cluster.b64 _, [ra];\n}"
               ::"r"(b), "r"(cta), "r"(pr) : "memory");
}
__device__ __forceinline__ void cluster_arrive() { asm volatile("barrier.cluster.arrive.aligned;" ::: "memory"); }
__device__ __forceinline__ void cluster_wait() { asm volatile("barrier.cluster.wait.aligned;" ::: "memory"); }
__device__ __forceinline__ void tma2d(uint32_t pr, uint32_t dst, const CUtensorMap* tm, uint32_t bar, int c0, int c1) {
  asm volatile(PRED_BEGIN(5) "@q cp.async.bulk.tensor.2d.shared::cluster.global.mbarrier::complete_tx::bytes [%0], [%1, {%3,%4}], [%2];\n}"
               ::"r"(dst), "l"(tm), "r"(bar), "r"(c0), "r"(c1), "r"(pr) : "memory");
}
__device__ __forceinline__ void tma2d_mc(uint32_t pr, uint32_t dst, const CUtensorMap* tm, uint32_t bar, int c0, int c1) {
  asm volatile(PRED_BEGIN(6) "@q cp.async.bulk.tensor.2d.shared::cluster.global.mbarrier::complete_tx::bytes.multicast::cluster [%0], [%1, {%3,%4}], [%2], %5;\n}"
               ::"r"(dst), "l"(tm), "r"(bar), "r"(c0), "r"(c1), "h"((uint16_t)3), "r"(pr) : "memory");
}
__device__ __forceinline__ void tma3d_mc(uint32_t pr, uint32_t dst, const CUtensorMap* tm, uint32_t bar, int c0, int c1, int c2) {
  asm volatile(PRED_BEGIN(7) "@q cp.async.bulk.tensor.3d.shared::cluster.global.mbarrier::complete_tx::bytes.multicast::cluster [%0], [%1, {%3,%4,%5}], [%2], %6;\n}"
               ::"r"(dst), "l"(tm), "r"(bar), "r"(c0), "r"(c1), "r"(c2), "h"((uint16_t)3), "r"(pr) : "memory");
}
__device__ __forceinline__ void prefetch_tm(const CUtensorMap* tm) { asm volatile("prefetch.tensormap [%0];" ::"l"(tm) : "memory"); }
__device__ __forceinline__ void wg_fence() { asm volatile("wgmma.fence.sync.aligned;" ::: "memory"); }
__device__ __forceinline__ void wg_commit() { asm volatile("wgmma.commit_group.sync.aligned;" ::: "memory"); }
template <int N> __device__ __forceinline__ void wg_wait() { asm volatile("wgmma.wait_group.sync.aligned %0;" ::"n"(N) : "memory"); }
__device__ __forceinline__ uint64_t mk_desc(uint32_t addr, uint32_t lbo, uint32_t sbo, uint32_t swz) {
  return (uint64_t)((addr & 0x3FFFF) >> 4) | ((uint64_t)(lbo >> 4) << 16) | ((uint64_t)(sbo >> 4) << 32) | ((uint64_t)swz << 62);
}
__device__ __forceinline__ void ldsm_x4(uint32_t& r0, uint32_t& r1, uint32_t& r2, uint32_t& r3, uint32_t addr) {
  asm volatile("ldmatrix.sync.aligned.m8n8.x4.shared.b16 {%0,%1,%2,%3}, [%4];" : "=r"(r0), "=r"(r1), "=r"(r2), "=r"(r3) : "r"(addr) : "memory");
}
__device__ __forceinline__ void ldsm_x4_t(uint32_t& r0, uint32_t& r1, uint32_t& r2, uint32_t& r3, uint32_t addr) {
  asm volatile("ldmatrix.sync.aligned.m8n8.x4.trans.shared.b16 {%0,%1,%2,%3}, [%4];" : "=r"(r0), "=r"(r1), "=r"(r2), "=r"(r3) : "r"(addr) : "memory");
}
__device__ __forceinline__ uint4 ldg128_coh(const void* p) {
  uint4 v; asm volatile("ld.global.v4.u32 {%0,%1,%2,%3}, [%4];" : "=r"(v.x), "=r"(v.y), "=r"(v.z), "=r"(v.w) : "l"(p) : "memory"); return v;
}
__device__ __forceinline__ void stsm_x4(uint32_t addr, uint32_t r0, uint32_t r1, uint32_t r2, uint32_t r3) {
  asm volatile("stmatrix.sync.aligned.m8n8.x4.shared.b16 [%0], {%1,%2,%3,%4};" ::"r"(addr), "r"(r0), "r"(r1), "r"(r2), "r"(r3) : "memory");
}
__device__ __forceinline__ void mma_f16(float (&c)[4], uint32_t a0, uint32_t a1, uint32_t a2, uint32_t a3, uint32_t b0, uint32_t b1) {
  asm volatile("mma.sync.aligned.m16n8k16.row.col.f32.f16.f16.f32 {%0,%1,%2,%3},{%4,%5,%6,%7},{%8,%9},{%0,%1,%2,%3};"
               : "+f"(c[0]), "+f"(c[1]), "+f"(c[2]), "+f"(c[3]) : "r"(a0), "r"(a1), "r"(a2), "r"(a3), "r"(b0), "r"(b1));
}
__device__ __forceinline__ uint4 lds128(uint32_t a) {
  uint4 v; asm volatile("ld.shared.v4.u32 {%0,%1,%2,%3}, [%4];" : "=r"(v.x), "=r"(v.y), "=r"(v.z), "=r"(v.w) : "r"(a) : "memory"); return v;
}
__device__ __forceinline__ uint32_t lds32(uint32_t a) { uint32_t v; asm volatile("ld.shared.u32 %0, [%1];" : "=r"(v) : "r"(a) : "memory"); return v; }
__device__ __forceinline__ void sts32(uint32_t a, uint32_t v) { asm volatile("st.shared.u32 [%0], %1;" ::"r"(a), "r"(v) : "memory"); }
__device__ __forceinline__ void stg128(void* p, uint4 v) {
  asm volatile("st.global.v4.u32 [%0], {%1,%2,%3,%4};" ::"l"(p), "r"(v.x), "r"(v.y), "r"(v.z), "r"(v.w) : "memory");
}
__device__ __forceinline__ uint32_t ldg32_coh(const void* p) {
  uint32_t v; asm volatile("ld.global.u32 %0, [%1];" : "=r"(v) : "l"(p) : "memory"); return v;
}
__device__ __forceinline__ void bar_sync(int id, int n) { asm volatile("bar.sync %0, %1;" ::"r"(id), "r"(n) : "memory"); }
__device__ __forceinline__ void flag_release(int lane, int f) {
  __syncwarp();
  asm volatile(PRED_BEGIN(1) "@q red.release.gpu.global.add.u32 [%0], 1;\n}" ::"l"(g_flags + f * 32), "r"((uint32_t)(lane == 0)) : "memory");
}
__device__ __forceinline__ void flag_wait(int f, unsigned target) {
  unsigned v;
#pragma unroll 1
  for (int i = 0; i < (1 << 24); i++) {
    asm volatile("ld.acquire.gpu.global.u32 %0, [%1];" : "=r"(v) : "l"(g_flags + f * 32) : "memory");
    if (v >= target) return;
    __nanosleep(32);
  }
  __trap();
}
__device__ __forceinline__ float bf_lo(uint32_t v) { return __uint_as_float(v << 16); }
__device__ __forceinline__ float bf_hi(uint32_t v) { return __uint_as_float(v & 0xffff0000u); }
__device__ __forceinline__ uint32_t pack_bf16(float lo, float hi) {
  uint32_t r; asm("cvt.rn.bf16x2.f32 %0, %1, %2;" : "=r"(r) : "f"(hi), "f"(lo)); return r;
}
__device__ __forceinline__ float bf16r(float x) { return bf_lo(pack_bf16(x, 0.f)); }
__device__ __forceinline__ uint32_t pack_f16(float lo, float hi) {
  uint32_t r; asm("cvt.rn.f16x2.f32 %0, %1, %2;" : "=r"(r) : "f"(hi), "f"(lo)); return r;
}
__device__ __forceinline__ uint32_t bmul2(uint32_t a, uint32_t b) { uint32_t r; asm("mul.rn.bf16x2 %0, %1, %2;" : "=r"(r) : "r"(a), "r"(b)); return r; }
__device__ __forceinline__ uint32_t badd2(uint32_t a, uint32_t b) { uint32_t r; asm("add.rn.bf16x2 %0, %1, %2;" : "=r"(r) : "r"(a), "r"(b)); return r; }
struct cf { float x, y; };
__device__ __forceinline__ cf cmul(cf a, cf b) { return {fmaf(a.x, b.x, -a.y * b.y), fmaf(a.x, b.y, a.y * b.x)}; }
__device__ __forceinline__ cf csq(cf a) { return {fmaf(a.x, a.x, -a.y * a.y), (a.x + a.x) * a.y}; }
__device__ __forceinline__ cf cexp2(float t2, float th) {
  float e; asm("ex2.approx.ftz.f32 %0, %1;" : "=f"(e) : "f"(t2));
  float k = rintf(th * 0.15915494309189535f);
  float r = fmaf(k, -6.28318548202514648f, th);
  r = fmaf(k, 1.74845553146951715e-7f, r);
  r = fmaf(k, 6.8604980400235275e-15f, r);
  return {e * __cosf(r), e * __sinf(r)};
}
__device__ __forceinline__ float pow2i(int e) {
  e = max(-126, min(127, e));
  return __int_as_float((e + 127) << 23);
}
__device__ __forceinline__ int exp_above(float v) { return ((__float_as_int(v) >> 23) & 0xff) - 126; }

__device__ __forceinline__ void wgmma_n256(float (&d)[128], uint64_t da, uint64_t db, int scale_d) {
  asm volatile("{\n.reg .pred p;\nsetp.ne.b32 p, %130, 0;\n"
    "wgmma.mma_async.sync.aligned.m64n256k16.f32.bf16.bf16 "
    "{%0,%1,%2,%3,%4,%5,%6,%7,%8,%9,%10,%11,%12,%13,%14,%15,%16,%17,%18,%19,%20,%21,%22,%23,%24,%25,%26,%27,%28,%29,%30,%31,%32,%33,%34,%35,%36,%37,%38,%39,%40,%41,%42,%43,%44,%45,%46,%47,%48,%49,%50,%51,%52,%53,%54,%55,%56,%57,%58,%59,%60,%61,%62,%63,%64,%65,%66,%67,%68,%69,%70,%71,%72,%73,%74,%75,%76,%77,%78,%79,%80,%81,%82,%83,%84,%85,%86,%87,%88,%89,%90,%91,%92,%93,%94,%95,%96,%97,%98,%99,%100,%101,%102,%103,%104,%105,%106,%107,%108,%109,%110,%111,%112,%113,%114,%115,%116,%117,%118,%119,%120,%121,%122,%123,%124,%125,%126,%127}, %128, %129, p, 1, 1, 0, 1;\n}\n"
    : "+f"(d[0]),"+f"(d[1]),"+f"(d[2]),"+f"(d[3]),"+f"(d[4]),"+f"(d[5]),"+f"(d[6]),"+f"(d[7]),"+f"(d[8]),"+f"(d[9]),"+f"(d[10]),"+f"(d[11]),"+f"(d[12]),"+f"(d[13]),"+f"(d[14]),"+f"(d[15]),"+f"(d[16]),"+f"(d[17]),"+f"(d[18]),"+f"(d[19]),"+f"(d[20]),"+f"(d[21]),"+f"(d[22]),"+f"(d[23]),"+f"(d[24]),"+f"(d[25]),"+f"(d[26]),"+f"(d[27]),"+f"(d[28]),"+f"(d[29]),"+f"(d[30]),"+f"(d[31]),"+f"(d[32]),"+f"(d[33]),"+f"(d[34]),"+f"(d[35]),"+f"(d[36]),"+f"(d[37]),"+f"(d[38]),"+f"(d[39]),"+f"(d[40]),"+f"(d[41]),"+f"(d[42]),"+f"(d[43]),"+f"(d[44]),"+f"(d[45]),"+f"(d[46]),"+f"(d[47]),"+f"(d[48]),"+f"(d[49]),"+f"(d[50]),"+f"(d[51]),"+f"(d[52]),"+f"(d[53]),"+f"(d[54]),"+f"(d[55]),"+f"(d[56]),"+f"(d[57]),"+f"(d[58]),"+f"(d[59]),"+f"(d[60]),"+f"(d[61]),"+f"(d[62]),"+f"(d[63]),"+f"(d[64]),"+f"(d[65]),"+f"(d[66]),"+f"(d[67]),"+f"(d[68]),"+f"(d[69]),"+f"(d[70]),"+f"(d[71]),"+f"(d[72]),"+f"(d[73]),"+f"(d[74]),"+f"(d[75]),"+f"(d[76]),"+f"(d[77]),"+f"(d[78]),"+f"(d[79]),"+f"(d[80]),"+f"(d[81]),"+f"(d[82]),"+f"(d[83]),"+f"(d[84]),"+f"(d[85]),"+f"(d[86]),"+f"(d[87]),"+f"(d[88]),"+f"(d[89]),"+f"(d[90]),"+f"(d[91]),"+f"(d[92]),"+f"(d[93]),"+f"(d[94]),"+f"(d[95]),"+f"(d[96]),"+f"(d[97]),"+f"(d[98]),"+f"(d[99]),"+f"(d[100]),"+f"(d[101]),"+f"(d[102]),"+f"(d[103]),"+f"(d[104]),"+f"(d[105]),"+f"(d[106]),"+f"(d[107]),"+f"(d[108]),"+f"(d[109]),"+f"(d[110]),"+f"(d[111]),"+f"(d[112]),"+f"(d[113]),"+f"(d[114]),"+f"(d[115]),"+f"(d[116]),"+f"(d[117]),"+f"(d[118]),"+f"(d[119]),"+f"(d[120]),"+f"(d[121]),"+f"(d[122]),"+f"(d[123]),"+f"(d[124]),"+f"(d[125]),"+f"(d[126]),"+f"(d[127])
    : "l"(da), "l"(db), "r"(scale_d));
}
__device__ __forceinline__ void wgmma_n192(float (&d)[128], uint64_t da, uint64_t db, int scale_d) {
  asm volatile("{\n.reg .pred p;\nsetp.ne.b32 p, %98, 0;\n"
    "wgmma.mma_async.sync.aligned.m64n192k16.f32.bf16.bf16 "
    "{%0,%1,%2,%3,%4,%5,%6,%7,%8,%9,%10,%11,%12,%13,%14,%15,%16,%17,%18,%19,%20,%21,%22,%23,%24,%25,%26,%27,%28,%29,%30,%31,%32,%33,%34,%35,%36,%37,%38,%39,%40,%41,%42,%43,%44,%45,%46,%47,%48,%49,%50,%51,%52,%53,%54,%55,%56,%57,%58,%59,%60,%61,%62,%63,%64,%65,%66,%67,%68,%69,%70,%71,%72,%73,%74,%75,%76,%77,%78,%79,%80,%81,%82,%83,%84,%85,%86,%87,%88,%89,%90,%91,%92,%93,%94,%95}, %96, %97, p, 1, 1, 0, 1;\n}\n"
    : "+f"(d[0]),"+f"(d[1]),"+f"(d[2]),"+f"(d[3]),"+f"(d[4]),"+f"(d[5]),"+f"(d[6]),"+f"(d[7]),"+f"(d[8]),"+f"(d[9]),"+f"(d[10]),"+f"(d[11]),"+f"(d[12]),"+f"(d[13]),"+f"(d[14]),"+f"(d[15]),"+f"(d[16]),"+f"(d[17]),"+f"(d[18]),"+f"(d[19]),"+f"(d[20]),"+f"(d[21]),"+f"(d[22]),"+f"(d[23]),"+f"(d[24]),"+f"(d[25]),"+f"(d[26]),"+f"(d[27]),"+f"(d[28]),"+f"(d[29]),"+f"(d[30]),"+f"(d[31]),"+f"(d[32]),"+f"(d[33]),"+f"(d[34]),"+f"(d[35]),"+f"(d[36]),"+f"(d[37]),"+f"(d[38]),"+f"(d[39]),"+f"(d[40]),"+f"(d[41]),"+f"(d[42]),"+f"(d[43]),"+f"(d[44]),"+f"(d[45]),"+f"(d[46]),"+f"(d[47]),"+f"(d[48]),"+f"(d[49]),"+f"(d[50]),"+f"(d[51]),"+f"(d[52]),"+f"(d[53]),"+f"(d[54]),"+f"(d[55]),"+f"(d[56]),"+f"(d[57]),"+f"(d[58]),"+f"(d[59]),"+f"(d[60]),"+f"(d[61]),"+f"(d[62]),"+f"(d[63]),"+f"(d[64]),"+f"(d[65]),"+f"(d[66]),"+f"(d[67]),"+f"(d[68]),"+f"(d[69]),"+f"(d[70]),"+f"(d[71]),"+f"(d[72]),"+f"(d[73]),"+f"(d[74]),"+f"(d[75]),"+f"(d[76]),"+f"(d[77]),"+f"(d[78]),"+f"(d[79]),"+f"(d[80]),"+f"(d[81]),"+f"(d[82]),"+f"(d[83]),"+f"(d[84]),"+f"(d[85]),"+f"(d[86]),"+f"(d[87]),"+f"(d[88]),"+f"(d[89]),"+f"(d[90]),"+f"(d[91]),"+f"(d[92]),"+f"(d[93]),"+f"(d[94]),"+f"(d[95])
    : "l"(da), "l"(db), "r"(scale_d));
}
__device__ __forceinline__ void wgmma_n128(float (&d)[64], uint64_t da, uint64_t db, int scale_d) {
  asm volatile("{\n.reg .pred p;\nsetp.ne.b32 p, %66, 0;\n"
    "wgmma.mma_async.sync.aligned.m64n128k16.f32.bf16.bf16 "
    "{%0,%1,%2,%3,%4,%5,%6,%7,%8,%9,%10,%11,%12,%13,%14,%15,%16,%17,%18,%19,%20,%21,%22,%23,%24,%25,%26,%27,%28,%29,%30,%31,%32,%33,%34,%35,%36,%37,%38,%39,%40,%41,%42,%43,%44,%45,%46,%47,%48,%49,%50,%51,%52,%53,%54,%55,%56,%57,%58,%59,%60,%61,%62,%63}, %64, %65, p, 1, 1, 0, 1;\n}\n"
    : "+f"(d[0]),"+f"(d[1]),"+f"(d[2]),"+f"(d[3]),"+f"(d[4]),"+f"(d[5]),"+f"(d[6]),"+f"(d[7]),"+f"(d[8]),"+f"(d[9]),"+f"(d[10]),"+f"(d[11]),"+f"(d[12]),"+f"(d[13]),"+f"(d[14]),"+f"(d[15]),"+f"(d[16]),"+f"(d[17]),"+f"(d[18]),"+f"(d[19]),"+f"(d[20]),"+f"(d[21]),"+f"(d[22]),"+f"(d[23]),"+f"(d[24]),"+f"(d[25]),"+f"(d[26]),"+f"(d[27]),"+f"(d[28]),"+f"(d[29]),"+f"(d[30]),"+f"(d[31]),"+f"(d[32]),"+f"(d[33]),"+f"(d[34]),"+f"(d[35]),"+f"(d[36]),"+f"(d[37]),"+f"(d[38]),"+f"(d[39]),"+f"(d[40]),"+f"(d[41]),"+f"(d[42]),"+f"(d[43]),"+f"(d[44]),"+f"(d[45]),"+f"(d[46]),"+f"(d[47]),"+f"(d[48]),"+f"(d[49]),"+f"(d[50]),"+f"(d[51]),"+f"(d[52]),"+f"(d[53]),"+f"(d[54]),"+f"(d[55]),"+f"(d[56]),"+f"(d[57]),"+f"(d[58]),"+f"(d[59]),"+f"(d[60]),"+f"(d[61]),"+f"(d[62]),"+f"(d[63])
    : "l"(da), "l"(db), "r"(scale_d));
}


constexpr int STAGE = 49152, NST = 4;
constexpr int NIT = 30;
static_assert(NST == 4, "x tile reuse assumes 4 slots");
constexpr int SM_RING = 0;
constexpr int U_PLANE = 146 * 16, U_CH = 2 * U_PLANE;
constexpr int CV_W = 8576, CV_PQ = 0, CV_KC = 2112, CV_Y = 0, CV_U = 3840;
constexpr int SM_CV = NST * STAGE;
constexpr int SM_GW = SM_CV + 4 * CV_W;
constexpr int SM_BAR = SM_GW + 1024;
constexpr int SMEM_TOTAL = SM_BAR + 96;
static_assert(SMEM_TOTAL <= 232448, "smem");
static_assert(CV_U + U_CH <= CV_W && CV_Y + 4096 <= CV_U + 256, "conv region");
constexpr int XY_PITCH = 144;

__device__ __forceinline__ int yswz(int l) { return l ^ (((l >> 6) & 1) << 3); }

template <int S> __device__ __forceinline__ int lat_s(int m) { return S == 0 ? m : 128 * S + ((m + ((1 << S) >> 1) - 1 + ((m >> S) & 1)) >> S); }
__device__ __forceinline__ int lat_any(int m) { return m < 256 ? m : m < 512 ? lat_s<1>(m) : m < 1024 ? lat_s<2>(m) : lat_s<3>(m); }

template <int S, bool ANYPREV>
__device__ __forceinline__ void expand4(uint32_t* dst, const unsigned short* kc, int m0) {
  const uint32_t k0 = kc[1 + (ANYPREV ? lat_any(m0 - 1) : lat_s<S>(m0 - 1))], k1 = kc[1 + lat_s<S>(m0)], k2 = kc[1 + lat_s<S>(m0 + 1)],
                 k3 = kc[1 + lat_s<S>(m0 + 2)], k4 = kc[1 + lat_s<S>(m0 + 3)];
  *reinterpret_cast<uint4*>(dst) = make_uint4(k1 | (k0 << 16), k2 | (k1 << 16), k3 | (k2 << 16), k4 | (k3 << 16));
}

__device__ __forceinline__ void near_table(uint32_t* Pq, const unsigned short* kc, int lane) {
  __syncwarp();
#pragma unroll
  for (int it = 0; it < 4; it++) {
    const int x = 4 * (lane + 32 * it);
    if (it < 2) expand4<0, false>(Pq + 16 + x, kc, x); else expand4<1, true>(Pq + 16 + x, kc, x);
  }
  if (lane < 4) *reinterpret_cast<uint4*>(Pq + 4 * lane) = make_uint4(0, 0, 0, 0);
}
__device__ __forceinline__ void conv_near(float (&acc)[16][4], uint32_t ubase, uint32_t* Pq, int lane) {
  __syncwarp();
  const uint32_t pa0 = smem_u32(Pq) + (16 + (lane >> 2) - 2 * (lane & 3)) * 4;
  const uint32_t fence_addr = smem_u32(Pq) - CV_PQ + CV_U - 8;
  uint32_t af[2][8][4], x[2][2][3];
  auto ld = [&](int b, int r) {
#pragma unroll
    for (int c = 0; c < 8; c++) ldsm_x4(af[b][c][0], af[b][c][1], af[b][c][2], af[b][c][3], ubase + (c * 16 - r) * 16);
#pragma unroll
    for (int q = 0; q < 2; q++) {
      const uint32_t p0 = pa0 + (256 * q + 16 * r) * 4;
      x[b][q][0] = lds32(p0); x[b][q][1] = lds32(p0 - 32); x[b][q][2] = lds32(p0 + 32);
    }
    sts32(fence_addr, 0u);
  };
  auto mm = [&](int b) {
#pragma unroll
    for (int q = 0; q < 2; q++) {
#pragma unroll
      for (int i = q; i < 8; i++) {
        mma_f16(acc[2 * i], af[b][i - q][0], af[b][i - q][1], af[b][i - q][2], af[b][i - q][3], x[b][q][0], x[b][q][1]);
        mma_f16(acc[2 * i + 1], af[b][i - q][0], af[b][i - q][1], af[b][i - q][2], af[b][i - q][3], x[b][q][2], x[b][q][0]);
      }
    }
  };
  ld(0, 0);
#pragma unroll 1
  for (int r = 0; r < 16; r += 2) { ld(1, r + 1); mm(0); ld(0, (r + 2) & 15); mm(1); }
}

constexpr int CV_E2 = 0, CV_P4 = 1056, CV_PA = CV_KC + 1296, CV_V1 = 0, CV_W1 = CV_KC, CV_W0 = CV_PA + 96;
static_assert(CV_W0 + 320 <= CV_U - 8 && CV_P4 + 256 <= CV_KC, "far tables");
__device__ __forceinline__ int far_off2(int o, int lam) {
  const int k = lat_s<2>(o + lam), kp = lat_s<2>(o + lam - 1);
  return 2 * (k - 256) - (k != kp ? 1 : 0) - 2 * (o >> 2);
}
__device__ __forceinline__ uint32_t band2(int j, int lo, int hi) {
  return ((j >= lo && j <= hi) ? 0x3c00u : 0u) | ((j - 1 >= lo && j - 1 <= hi) ? 0x3c000000u : 0u);
}
template <int LO, int HI, int ND>
__device__ __forceinline__ void window_sums(float (&v)[8][4], uint32_t ubase, int lam) {
#pragma unroll
  for (int i = 0; i < 8; i++) v[i][0] = v[i][1] = v[i][2] = v[i][3] = 0.f;
#pragma unroll
  for (int dl = 0; dl < ND; dl++) {
    const uint32_t x0 = band2(16 * dl + lam, LO, HI), xm = band2(16 * dl - 8 + lam, LO, HI), xp = band2(16 * dl + 8 + lam, LO, HI);
#pragma unroll
    for (int c = 0; c < 4; c++) {
      uint32_t a0, a1, a2, a3;
      ldsm_x4(a0, a1, a2, a3, ubase + (c * 16 - dl) * 16);
      mma_f16(v[2 * c], a0, a1, a2, a3, x0, xm);
      mma_f16(v[2 * c + 1], a0, a1, a2, a3, xp, x0);
    }
  }
}
__device__ __forceinline__ void store_v(const float (&v)[8][4], uint32_t dst, int lane) {
  const uint32_t p = dst + (lane >> 2) * 16 + (lane & 3) * 4;
#pragma unroll
  for (int i = 0; i < 8; i++) {
    sts32(p + (i & 1) * 1024 + (i >> 1) * 256, pack_f16(v[i][0], v[i][1]));
    sts32(p + (i & 1) * 1024 + (i >> 1) * 256 + 128, pack_f16(v[i][2], v[i][3]));
  }
}
__device__ __forceinline__ void conv_far(float (&acc)[16][4], uint32_t ubase, uint8_t* wreg, uint32_t wb, const unsigned short* kc, int lane) {
  __syncwarp();
#pragma unroll
  for (int it = 0; it < 5; it++) {
    const int k = 126 + it * 32 + lane;
    if (k <= 256) {
      const uint32_t a1 = kc[257 + k], a0 = kc[256 + k];
      *reinterpret_cast<uint2*>(wreg + CV_E2 + (2 * k - 252) * 4) = make_uint2(a1 | (a0 << 16), a1 * 0x10001u);
    }
  }
  {
    const int m = lane < 24 ? 496 + lane : 0;
    if (lane < 24) reinterpret_cast<uint32_t*>(wreg + CV_PA)[lane] = (uint32_t)kc[1 + lat_any(m)] | ((uint32_t)kc[1 + lat_any(m - 1)] << 16);
#pragma unroll
    for (int h = 0; h < 2; h++) {
      const int m4 = 1008 + h * 32 + lane;
      const uint32_t k1 = m4 <= 1028 ? kc[1 + lat_any(m4)] : 0u, k0 = m4 - 1 <= 1028 ? kc[1 + lat_any(m4 - 1)] : 0u;
      reinterpret_cast<uint32_t*>(wreg + CV_P4)[h * 32 + lane] = k1 | (k0 << 16);
    }
  }
  uint32_t pw1[3], pw0[3];
#pragma unroll
  for (int h = 0; h < 3; h++) {
    const int n = 48 + h * 32 + lane;
    const bool in1 = n >= 64 && n <= 127, in0 = n - 1 >= 64 && n - 1 <= 127;
    const int nn = min(n, 127);
    pw1[h] = (in1 ? (uint32_t)kc[386 + 2 * nn] : 0u) | (in0 ? (uint32_t)kc[384 + 2 * nn] << 16 : 0u);
    pw0[h] = (in1 ? (uint32_t)kc[387 + 2 * nn] : 0u) | (in0 ? (uint32_t)kc[385 + 2 * nn] << 16 : 0u);
  }
  __syncwarp();
#pragma unroll
  for (int h = 0; h < 3; h++) {
    if (h * 32 + lane < 80) {
      reinterpret_cast<uint32_t*>(wreg + CV_W1)[h * 32 + lane] = pw1[h];
      reinterpret_cast<uint32_t*>(wreg + CV_W0)[h * 32 + lane] = pw0[h];
    }
  }
  __syncwarp();
  const int lam = (lane >> 2) - 2 * (lane & 3);
  const uint32_t e2 = wb + CV_E2 + (far_off2(640, lam) - 251) * 4;
  const uint32_t pa = wb + CV_PA + (16 + lam) * 4, p4 = wb + CV_P4 + (16 + lam) * 4;
  {
    uint32_t af[2][6][4], x[2][2][3];
    auto ld = [&](int b, int r, bool first) {
#pragma unroll
      for (int c = 0; c < 6; c++) ldsm_x4(af[b][c][0], af[b][c][1], af[b][c][2], af[b][c][3], ubase + (c * 16 - r) * 16);
#pragma unroll
      for (int q = 2; q < 4; q++) {
        uint32_t c0 = e2 + (128 * q + 8 * r) * 4, cp = c0 + 16, cm = c0 - 16;
        if (q == 2 && first) { c0 = pa; cm = pa - 32; }
        x[b][q - 2][0] = lds32(c0); x[b][q - 2][1] = lds32(cm); x[b][q - 2][2] = lds32(cp);
      }
      sts32(wb + CV_U - 8, 0u);
    };
    auto mm = [&](int b) {
#pragma unroll
      for (int q = 2; q < 4; q++) {
#pragma unroll
        for (int i = q; i < 8; i++) {
          mma_f16(acc[2 * i], af[b][i - q][0], af[b][i - q][1], af[b][i - q][2], af[b][i - q][3], x[b][q - 2][0], x[b][q - 2][1]);
          mma_f16(acc[2 * i + 1], af[b][i - q][0], af[b][i - q][1], af[b][i - q][2], af[b][i - q][3], x[b][q - 2][2], x[b][q - 2][0]);
        }
      }
    };
    ld(0, 0, true);
#pragma unroll 1
    for (int r = 0; r < 16; r += 2) { ld(1, r + 1, false); mm(0); ld(0, r < 14 ? r + 2 : 2, false); mm(1); }
  }
#pragma unroll
  for (int r = 0; r < 2; r++) {
    const uint32_t x0 = lds32(p4 + r * 64), xm = lds32(p4 + r * 64 - 32), xp = lds32(p4 + r * 64 + 32);
#pragma unroll
    for (int c = 0; c < 4; c++) {
      uint32_t a0, a1, a2, a3;
      ldsm_x4(a0, a1, a2, a3, ubase + (c * 16 - r) * 16);
      mma_f16(acc[2 * (4 + c)], a0, a1, a2, a3, x0, xm);
      mma_f16(acc[2 * (4 + c) + 1], a0, a1, a2, a3, xp, x0);
    }
  }
  {
    float v[8][4];
    window_sums<5, 11, 2>(v, ubase, lam);
    __syncwarp();
    store_v(v, wb + CV_V1, lane);
    window_sums<12, 20, 3>(v, ubase, lam);
    __syncwarp();
    store_v(v, wb + CV_U, lane);
    __syncwarp();
  }
#pragma unroll
  for (int arr = 0; arr < 2; arr++) {
    const uint32_t vb = wb + (arr ? CV_V1 : CV_U) + (lane >> 4) * 1024 + (lane & 15) * 16;
    const uint32_t pw = wb + (arr ? CV_W1 : CV_W0) + (16 + lam) * 4;
    uint32_t bf[4][4];
#pragma unroll
    for (int kp = 0; kp < 4; kp++) ldsm_x4_t(bf[kp][0], bf[kp][1], bf[kp][2], bf[kp][3], vb + kp * 256);
#pragma unroll
    for (int dd = 0; dd < 4; dd++) {
      const uint32_t a0 = lds32(pw + dd * 64), a1 = lds32(pw + dd * 64 + 32), a2 = lds32(pw + dd * 64 - 32);
#pragma unroll
      for (int kp = 0; kp + dd < 4; kp++) {
        mma_f16(acc[2 * (4 + dd + kp)], a0, a1, a2, a0, bf[kp][0], bf[kp][1]);
        mma_f16(acc[2 * (4 + dd + kp) + 1], a0, a1, a2, a0, bf[kp][2], bf[kp][3]);
      }
    }
  }
}

struct Params {
  const __nv_bfloat16 *u, *logAr, *Aim, *Cre, *Cim, *logdt, *Dsk, *gw;
  __nv_bfloat16* out;
};

__device__ __forceinline__ float sel16(uint2 v, int rd) {
  const uint32_t w = (rd & 2) ? v.y : v.x;
  return __uint_as_float((rd & 1) ? (w & 0xffff0000u) : (w << 16));
}
__device__ __forceinline__ void quad_transpose(uint32_t (&v)[4], int t);

struct KParams { uint2 vl, va, vr, vi; float ldt; };
__device__ __forceinline__ KParams kgen_load(const Params& p, int d, int lane) {
  KParams k;
  k.vl = __ldg(reinterpret_cast<const uint2*>(p.logAr + d * NS_) + lane);
  k.va = __ldg(reinterpret_cast<const uint2*>(p.Aim + d * NS_) + lane);
  k.vr = __ldg(reinterpret_cast<const uint2*>(p.Cre + d * NS_) + lane);
  k.vi = __ldg(reinterpret_cast<const uint2*>(p.Cim + d * NS_) + lane);
  k.ldt = __bfloat162float(p.logdt[d]);
  return k;
}
__device__ __forceinline__ void kgen(const KParams& k, int rd0, int rd1, uint8_t* stg, int lane, float (&kacc)[5][4], int& ec, float& k0) {
  const float dt = bf16r(expf(k.ldt));
  float sa = 0.f, sr = 0.f;
#pragma unroll
  for (int rd = 0; rd < 4; rd++) {
    const float a = sel16(k.vr, rd) * dt, b = sel16(k.vi, rd) * dt;
    sa += fabsf(a) + fabsf(b); sr += a;
  }
#pragma unroll
  for (int o = 16; o; o >>= 1) { sa += __shfl_xor_sync(0xffffffffu, sa, o); sr += __shfl_xor_sync(0xffffffffu, sr, o); }
  ec = exp_above(sa);
  const float sx = pow2i(15 - ec);
  k0 = sr * sx;
  const uint32_t pb = smem_u32(stg);
#pragma unroll
  for (int i = 0; i < 5; i++) kacc[i][0] = kacc[i][1] = kacc[i][2] = kacc[i][3] = 0.f;
#pragma unroll 1
  for (int rd = rd0; rd < rd1; rd++) {
    const float zr = -bf16r(expf(sel16(k.vl, rd))) * dt, zi = sel16(k.va, rd) * dt;
    const cf C = {sel16(k.vr, rd) * dt * sx, sel16(k.vi, rd) * dt * sx};
    const float t2 = zr * 1.4426950408889634f;
    const cf w1 = cexp2(t2, zi), q1 = cexp2(t2 * 8.f, zi * 8.f), r1 = cexp2(t2 * 128.f, zi * 128.f);
    uint32_t* const xy = reinterpret_cast<uint32_t*>(stg) + lane;
    constexpr int XP = XY_PITCH / 4;
    __syncwarp();
    {
      cf q[16];
      q[1] = {q1.x, -q1.y};
#pragma unroll
      for (int b = 2; b < 16; b++) q[b] = (b & 1) ? cmul(q[b >> 1], q[b - (b >> 1)]) : csq(q[b >> 1]);
      xy[0] = 0x00003c00u;
#pragma unroll
      for (int b = 1; b < 16; b++) xy[b * XP] = pack_f16(q[b].x, q[b].y);
    }
    cf cwv[9];
    {
      cf w[9];
      w[1] = w1; w[8] = q1;
#pragma unroll
      for (int b = 2; b < 8; b++) w[b] = (b & 1) ? cmul(w[b >> 1], w[b - (b >> 1)]) : csq(w[b >> 1]);
#pragma unroll
      for (int b = 1; b <= 8; b++) cwv[b] = cmul(C, w[b]);
    }
    cf r[16];
    r[1] = r1;
#pragma unroll
    for (int a = 2; a < 16; a++) r[a] = (a & 1) ? cmul(r[a >> 1], r[a - (a >> 1)]) : csq(r[a >> 1]);
    auto put = [&](int row, cf v) { xy[(16 + row) * XP] = pack_f16(v.x, v.y); };
    const uint32_t aaddr = pb + (lane & 15) * XY_PITCH + (lane >> 4) * 16;
    const uint32_t baddr = pb + (16 + (lane & 7)) * XY_PITCH + (lane >> 3) * 16;
    uint32_t af[4][4];
    auto mmas = [&](int t0, int nt) {
#pragma unroll
      for (int tile = 0; tile < nt; tile++) {
#pragma unroll
        for (int k2 = 0; k2 < 2; k2++) {
          uint32_t b0, b1, b2, b3;
          ldsm_x4(b0, b1, b2, b3, baddr + tile * 8 * XY_PITCH + k2 * 64);
          mma_f16(kacc[t0 + tile], af[2 * k2][0], af[2 * k2][1], af[2 * k2][2], af[2 * k2][3], b0, b1);
          mma_f16(kacc[t0 + tile], af[2 * k2 + 1][0], af[2 * k2 + 1][1], af[2 * k2 + 1][2], af[2 * k2 + 1][3], b2, b3);
        }
      }
    };
#pragma unroll
    for (int c = 0; c < 8; c++) {
      put(c, cwv[c + 1]);
      put(8 + c, cmul(cwv[c + 1], r[1]));
      put(16 + c, cmul(cwv[2 * (c & 3) + 2], r[2 + (c >> 2)]));
    }
    __syncwarp();
#pragma unroll
    for (int k = 0; k < 4; k++) ldsm_x4(af[k][0], af[k][1], af[k][2], af[k][3], aaddr + k * 32);
    mmas(0, 3);
    __syncwarp();
#pragma unroll
    for (int c = 0; c < 8; c++) {
      put(c, cmul(cwv[4 * (c & 1) + 4], r[4 + (c >> 1)]));
      put(8 + c, cmul(cwv[8], r[8 + c]));
    }
    __syncwarp();
    mmas(3, 2);
  }
  __syncwarp();
}
constexpr int SM_HELP = SM_RING + 3 * STAGE, HELP_W = 6144;
constexpr int BAR_XT = SM_BAR + 16 * NST, BAR_KB = BAR_XT + 8, BAR_KB2 = BAR_XT + 16, BAR_C1 = BAR_XT + 24;
__device__ __forceinline__ void mbar_arrive_local(uint32_t pr, uint32_t b) {
  asm volatile(PRED_BEGIN(1) "@q mbarrier.arrive.shared::cta.b64 _, [%0];\n}" ::"r"(b), "r"(pr) : "memory");
}

__device__ __forceinline__ void conv_role(const Params& p, uint8_t* sg, uint32_t sb, int lane, int cw, float (&kacc)[5][4], const int ec, const float k0) {
  const int g = lane >> 2, t = lane & 3;
  const int d0 = blockIdx.x * 4, d = d0 + cw;
  int eu;
  const uint32_t pb = sb + SM_CV + cw * CV_W;
  uint8_t* const wg_ = sg + SM_CV + cw * CV_W;
  unsigned short* const kc = reinterpret_cast<unsigned short*>(wg_ + CV_KC);
  uint4 ur[8];
  mbar_wait(sb + BAR_KB, 0);
#pragma unroll
  for (int h = 0; h < 2; h++) {
#pragma unroll
    for (int i = 0; i < 5; i++) {
      const float4 v = *reinterpret_cast<const float4*>(sg + SM_HELP + (cw + 4 * h) * HELP_W + (i * 32 + lane) * 16);
      kacc[i][0] += v.x; kacc[i][1] += v.y; kacc[i][2] += v.z; kacc[i][3] += v.w;
    }
  }
  __syncwarp();
  mbar_arrive_cta(lane < 2, sb + BAR_KB2, lane & 1);
  {
    mbar_wait(sb + SM_BAR, 0);
    const int fs = blockIdx.x >> 4, mt1 = 2 * ((blockIdx.x >> 1) & 7) + (blockIdx.x & 1);
#pragma unroll
    for (int h = 0; h < 2; h++) {
      __nv_bfloat16* up = g_ut + (size_t)(fs * 64 + (cw * 2 + h) * 8 + g) * L_ + mt1 * 128 + t * 8;
#pragma unroll
      for (int k = 0; k < 4; k++) {
        uint32_t v[4];
        const int row = k * 32 + lane;
        ldsm_x4_t(v[0], v[1], v[2], v[3], sb + SM_RING + row * 128 + (((cw * 2 + h) ^ (row & 7)) << 4));
        quad_transpose(v, t);
        stg128(up + k * 32, make_uint4(v[0], v[1], v[2], v[3]));
      }
    }
    __syncwarp();
    mbar_arrive_local(lane == 0, sb + BAR_XT);
  }
#pragma unroll
  for (int e = 0; e < 4; e++) {
    const int col = 2 * t + (e & 1), lo = g + 8 * (e >> 1);
    kc[2 + col + 8 * lo] = (unsigned short)pack_f16(kacc[0][e], 0.f);
    kc[130 + col + 8 * lo] = (unsigned short)pack_f16(kacc[1][e], 0.f);
    kc[258 + 64 * (col >> 2) + (col & 3) + 4 * lo] = (unsigned short)pack_f16(kacc[2][e], 0.f);
    kc[386 + 32 * (col >> 1) + (col & 1) + 2 * lo] = (unsigned short)pack_f16(kacc[3][e], 0.f);
    kc[514 + 16 * col + lo] = (unsigned short)pack_f16(kacc[4][e], 0.f);
  }
  if (lane == 0) { kc[0] = 0; kc[1] = (unsigned short)pack_f16(k0, 0.f); }
  near_table(reinterpret_cast<uint32_t*>(wg_ + CV_PQ), kc, lane);
  flag_release(lane, FL_UT + (blockIdx.x >> 4));
  {
    flag_wait(FL_UT + (d >> 6), 64);
#pragma unroll
    for (int k = 0; k < 8; k++) ur[k] = ldg128_coh(g_ut + (size_t)d * L_ + (lane + 32 * k) * 8);
    uint32_t mx = 0;
#pragma unroll
    for (int k = 0; k < 8; k++) {
      const uint32_t w[4] = {ur[k].x, ur[k].y, ur[k].z, ur[k].w};
#pragma unroll
      for (int e = 0; e < 4; e++) mx = max(mx, max(w[e] & 0x7fff0000u, (w[e] << 16) & 0x7fff0000u));
    }
    mx = __reduce_max_sync(0xffffffffu, mx);
    eu = exp_above(__uint_as_float(mx));
    const float sc = pow2i(11 - eu);
    *reinterpret_cast<uint4*>(wg_ + CV_U + (lane >> 4) * U_PLANE + (lane & 15) * 16) = make_uint4(0, 0, 0, 0);
#pragma unroll
    for (int k = 0; k < 8; k++) {
      const int i8 = lane + 32 * k;
      uint4 o;
      o.x = pack_f16(bf_lo(ur[k].x) * sc, bf_hi(ur[k].x) * sc); o.y = pack_f16(bf_lo(ur[k].y) * sc, bf_hi(ur[k].y) * sc);
      o.z = pack_f16(bf_lo(ur[k].z) * sc, bf_hi(ur[k].z) * sc); o.w = pack_f16(bf_lo(ur[k].w) * sc, bf_hi(ur[k].w) * sc);
      *reinterpret_cast<uint4*>(wg_ + CV_U + (i8 & 1) * U_PLANE + (16 + (i8 >> 1)) * 16) = o;
    }
  }
  {
    float acc[16][4];
#pragma unroll
    for (int i = 0; i < 16; i++) { acc[i][0] = acc[i][1] = acc[i][2] = acc[i][3] = 0.f; }
    const uint32_t ubase = pb + CV_U + (lane >> 4) * U_PLANE + (16 + (lane & 15)) * 16;
    conv_near(acc, ubase, reinterpret_cast<uint32_t*>(wg_ + CV_PQ), lane);
    mbar_arrive_local(lane == 0, sb + BAR_C1);
    conv_far(acc, ubase, wg_, pb, kc, lane);
#pragma unroll
    for (int k = 0; k < 8; k++) ur[k] = ldg128_coh(g_ut + (size_t)d * L_ + (lane + 32 * k) * 8);
    __syncwarp();
    const float s1 = pow2i(ec - 14), s2 = pow2i(eu - 11);
#pragma unroll
    for (int i = 0; i < 16; i++) {
      const int l = 256 * (i >> 1) + 16 * g + 8 * (i & 1) + 2 * t;
      *reinterpret_cast<uint32_t*>(wg_ + CV_Y + yswz(l) * 2) = pack_bf16((acc[i][0] * s1) * s2, (acc[i][1] * s1) * s2);
      *reinterpret_cast<uint32_t*>(wg_ + CV_Y + yswz(l + 128) * 2) = pack_bf16((acc[i][2] * s1) * s2, (acc[i][3] * s1) * s2);
    }
  }
  __syncwarp();
  {
    const uint32_t dsk = (uint32_t)__ldg(reinterpret_cast<const unsigned short*>(p.Dsk) + d) * 0x10001u;
#pragma unroll
    for (int k = 0; k < 8; k++) {
      const int i8 = lane + 32 * k;
      const uint4 y = *reinterpret_cast<const uint4*>(wg_ + CV_Y + yswz(i8 * 8) * 2);
      __syncwarp();
      *reinterpret_cast<uint4*>(wg_ + CV_Y + i8 * 16) = make_uint4(badd2(y.x, bmul2(ur[k].x, dsk)), badd2(y.y, bmul2(ur[k].y, dsk)),
                                                                   badd2(y.z, bmul2(ur[k].z, dsk)), badd2(y.w, bmul2(ur[k].w, dsk)));
    }
    asm volatile("fence.proxy.async.shared::cta;" ::: "memory");
    __syncwarp();
    asm volatile(PRED_BEGIN(2) "@q cp.async.bulk.global.shared::cta.bulk_group [%0], [%1], 4096;\n"
                 "@q cp.async.bulk.commit_group;\n@q cp.async.bulk.wait_group 0;\n}"
                 ::"l"(g_a + (size_t)d * L_), "r"(pb + CV_Y), "r"((uint32_t)(lane == 0)) : "memory");
  }
  asm volatile(PRED_BEGIN(1) "@q red.relaxed.gpu.global.add.u32 [%0], 1;\n}" ::"l"(g_flags + (FL_CONV + (d >> 7)) * 32), "r"((uint32_t)(lane == 0)) : "memory");
}

struct Maps { CUtensorMap x, g2, u2, g3, u3, h, wd, at; };

struct Ctx {
  uint32_t sb, full, empty, rank;
  unsigned fv;
  int mt1, fs, nt2, mt2, warp;
};

__device__ __forceinline__ int g2_block(int it) {
  if (it < 16) { const int b = it & 3; return 7 * (it >> 2) + (b < 2 ? b : b + 3); }
  const int i2 = it - 16, q = (i2 * 43) >> 7;
  return 7 * q + 2 + (i2 - 3 * q);
}
__device__ __forceinline__ void load_iter(const Maps& m, const Ctx& c, int n, int s, int part, uint32_t pr, unsigned& fv) {
  const uint32_t st = c.sb + SM_RING + s * STAGE, fb = c.full + 8 * s;
  if (n < 16) {
    const int kb = (((n < 8 ? n : n + 4) + c.fs) & 7) * 64;
    if (part == 3) {
      mbar_expect_tx(pr, fb, n < 8 ? 49152 : n < 12 ? 24576 : 16384 + 24576);
    } else if (part == 2) {
      if (n == 4) mbar_wait(c.sb + BAR_XT, 0);
      if (n < 8 || n >= 12) tma2d(pr, st, &m.x, fb, kb, c.mt1 * 128);
    } else if (n < 8) {
      const int col = c.fs * 224 + ((c.fs & 1) ? 96 : 0);
      tma2d_mc(pr, st + 16384 + c.rank * 16384 + part * 8192, c.rank ? &m.u2 : &m.g2, fb, col + part * 64, kb);
    } else if (part == 0) {
      tma3d_mc(pr, st + 16384 + c.rank * 12288, c.rank ? &m.u3 : &m.g3, fb, 0, kb, c.fs * 7 + ((c.fs & 1) ? 0 : 4));
    }
  } else if (n == NIT) {
    if (part == 2) {
      if (fv < 128) flag_wait(FL_CONV + c.nt2, 128);
      asm volatile("fence.proxy.async.global;" ::: "memory");
      mbar_expect_tx(pr, fb, 16384);
      tma2d(pr, st, &m.at, fb, c.mt2 * 64, c.nt2 * 128);
    }
  } else {
    const int it = 2 * (n - 16);
    const int kk = g2_block(it + (part & 1)) * 64;
    if (part < 2) {
      if (part == 0) mbar_expect_tx(pr, fb, 49152);
      tma2d_mc(pr, st + part * 24576 + 8192 + c.rank * 8192, &m.wd, fb, c.nt2 * 128 + c.rank * 64, kk);
    } else {
      if (it == 0 || it == 16) {
        if (fv < 8) flag_wait((it ? FL_H2 : FL_H1) + (c.mt2 >> 1), 8);
        asm volatile("fence.proxy.async.global;" ::: "memory");
      }
      tma2d(pr, st + (part & 1) * 24576, &m.h, fb, kk, c.mt2 * 64);
    }
  }
  if (part >= 2 && (n == 15 || n == 23 || n == NIT - 1)) {
    const int f = n == 15 ? FL_H1 + (c.mt2 >> 1) : n == 23 ? FL_H2 + (c.mt2 >> 1) : FL_CONV + c.nt2;
    asm volatile("ld.relaxed.gpu.global.u32 %0, [%1];" : "=r"(fv) : "l"(g_flags + f * 32) : "memory");
  }
}
__device__ __forceinline__ void stores_done(int warp) {
  if (warp != 7) asm volatile("bar.arrive 3, 256;" ::: "memory");
}
__device__ __forceinline__ void publish(int tid, int warp, int f) {
  if (warp == 7) {
    asm volatile("bar.sync 3, 256;" ::: "memory");
    flag_release(tid & 31, f);
  }
}
__device__ __forceinline__ void release_refill(const Maps& m, Ctx& c, int tid, int n) {
  if (n + NST <= NIT) {
    const int s = n & 3;
    mbar_arrive_cta((tid & 127) < 2, c.empty + 8 * s, tid & 1);
    if (c.warp < 4) {
      mbar_wait(c.empty + 8 * s, (n >> 2) & 1);
      load_iter(m, c, n + NST, s, c.warp, (tid & 31) == 0, c.fv);
    }
  }
}

__device__ __forceinline__ void quad_transpose(uint32_t (&v)[4], int t) {
  const bool o1 = t & 1, o2 = t & 2;
  uint32_t a = o1 ? v[0] : v[1], b = o1 ? v[2] : v[3];
  a = __shfl_xor_sync(0xffffffffu, a, 1); b = __shfl_xor_sync(0xffffffffu, b, 1);
  if (o1) { v[0] = a; v[2] = b; } else { v[1] = a; v[3] = b; }
  a = o2 ? v[0] : v[2]; b = o2 ? v[1] : v[3];
  a = __shfl_xor_sync(0xffffffffu, a, 2); b = __shfl_xor_sync(0xffffffffu, b, 2);
  if (o2) { v[0] = a; v[1] = b; } else { v[2] = a; v[3] = b; }
}

template <int PASS>
__device__ __forceinline__ void g1_pass(float (&acc)[128], const Maps& m, Ctx& c, int tid, int& pend) {
  const int lane = tid & 31, warp = c.warp, wg = warp >> 2;
  const int g = lane >> 2, t = lane & 3;
  constexpr int NJ = PASS ? 12 : 16;
  float gs0 = 0.f, gs1 = 0.f;
  const int grow = c.fs * 16 + warp * 2;
  const uint32_t goff0 = grow * 128 + ((((lane >> 2) ^ (grow & 7))) << 4) + (lane & 3) * 4;
  const uint32_t goff1 = (grow + 1) * 128 + ((((lane >> 2) ^ ((grow + 1) & 7))) << 4) + (lane & 3) * 4;
#pragma unroll 1
  for (int i = 0; i < 8; i++) {
    const int n = PASS * 8 + i;
    mbar_wait(c.full + 8 * (n & 3), (n >> 2) & 1);
    const uint32_t st = c.sb + SM_RING + (n & 3) * STAGE;
    const uint64_t da = mk_desc(st + wg * 8192, 16, 1024, 1);
    const uint64_t db = PASS ? mk_desc(st + 16384, 4096, 512, 2) : mk_desc(st + 16384, 8192, 1024, 1);
    wg_fence();
#pragma unroll
    for (int k = 0; k < 4; k++) {
      if (PASS == 0) wgmma_n256(acc, da + k * 2, db + k * 128, (i | k) != 0);
      else wgmma_n192(acc, da + k * 2, db + k * 64, (i | k) != 0);
    }
    wg_commit();
    if (PASS == 0 && i == 0 && warp < 4) {
      mbar_wait(c.sb + BAR_KB2, 0);
      asm volatile("fence.proxy.async.shared::cta;" ::: "memory");
      load_iter(m, c, 3, 3, warp, lane == 0, c.fv);
    }
    if (PASS == 0) {
      const uint32_t gw = lds32(c.sb + SM_GW + ((i + c.fs) & 7) * 128 + lane * 4);
      const uint32_t p0 = bmul2(lds32(st + goff0), gw), p1 = bmul2(lds32(st + goff1), gw);
      gs0 += bf_lo(p0) + bf_hi(p0); gs1 += bf_lo(p1) + bf_hi(p1);
    }
    if (i > 0) {
      wg_wait<1>();
      release_refill(m, c, tid, n - 1);
    }
  }
  wg_wait<0>();
  release_refill(m, c, tid, PASS * 8 + 7);
  const int col0 = c.fs * 224 + ((c.fs & 1) ? (PASS ? 0 : 96) : (PASS ? 128 : 0));
  __nv_bfloat16* hp = g_h + (size_t)(c.mt1 * 128 + warp * 16 + g) * F_ + col0 + t * 8;
#pragma unroll
  for (int j4 = 0; j4 < NJ; j4 += 4) {
    uint32_t r0[4], r1[4];
#pragma unroll
    for (int e = 0; e < 4; e++) {
      const float* gp = acc + (j4 + e) * 4;
      const float* up = acc + (j4 + e + NJ) * 4;
      r0[e] = bmul2(pack_bf16(gp[0], gp[1]), pack_bf16(up[0], up[1]));
      r1[e] = bmul2(pack_bf16(gp[2], gp[3]), pack_bf16(up[2], up[3]));
    }
    quad_transpose(r0, t); quad_transpose(r1, t);
    stg128(hp + j4 * 8, make_uint4(r0[0], r0[1], r0[2], r0[3]));
    stg128(hp + (size_t)8 * F_ + j4 * 8, make_uint4(r1[0], r1[1], r1[2], r1[3]));
  }
  if (PASS == 0) {
#pragma unroll
    for (int o = 16; o; o >>= 1) { gs0 += __shfl_xor_sync(0xffffffffu, gs0, o); gs1 += __shfl_xor_sync(0xffffffffu, gs1, o); }
    const float sv = bf16r((lane & 1) ? gs1 : gs0);
    const float gt = bf16r(1.f / (1.f + expf(-sv)));
    if (lane < 2) g_gate[c.mt1 * 128 + grow + lane] = pack_bf16(gt, 1.f - gt);
  }
  stores_done(warp);
  pend = (PASS ? FL_H2 : FL_H1) + c.mt1;
}

__global__ void __cluster_dims__(2, 1, 1) __launch_bounds__(384, 1)
fused_kernel(const __grid_constant__ Maps m, const Params p) {
  extern __shared__ uint8_t sm_raw[];
  Ctx c;
  c.sb = smem_u32(sm_raw);
  if (c.sb & 1023u) __trap();
  c.full = c.sb + SM_BAR; c.empty = c.full + 8 * NST;
  const uint32_t sb = c.sb;
  const int tid = threadIdx.x, lane = tid & 31, warp = __shfl_sync(0xffffffffu, tid >> 5, 0), wg = warp >> 2;
  c.warp = warp;
  c.rank = blockIdx.x & 1; c.fv = 0;
  const int pair = blockIdx.x >> 1;
  c.mt1 = 2 * (pair & 7) + c.rank; c.fs = pair >> 3;
  c.nt2 = pair & 3; c.mt2 = 2 * (pair >> 2) + c.rank;
  const KParams kp = kgen_load(p, blockIdx.x * 4 + (warp & 3), lane);
  const uint32_t gwv = wg < 2 ? __ldg(reinterpret_cast<const uint32_t*>(p.gw) + tid) : 0u;
  if (tid == 0) {
    for (int s = 0; s < NST; s++) { mbar_init(c.full + 8 * s, 1); mbar_init(c.empty + 8 * s, 4); }
    mbar_init(sb + BAR_XT, 4); mbar_init(sb + BAR_KB, 8); mbar_init(sb + BAR_KB2, 8); mbar_init(sb + BAR_C1, 4);
    asm volatile("fence.mbarrier_init.release.cluster;\nfence.proxy.async.shared::cta;" ::: "memory");
  }
  if (tid == 32) { prefetch_tm(&m.x); prefetch_tm(&m.g2); prefetch_tm(&m.u2); }
  __syncwarp();
  asm volatile("barrier.cluster.arrive.relaxed.aligned;" ::: "memory");
  cluster_wait();
  if (warp < 4) {
#pragma unroll 1
    for (int n = 0; n < 3; n++) load_iter(m, c, n, n, warp, lane == 0, c.fv);
  }
  float kacc[5][4], k0;
  int ec;
  kgen(kp, wg == 2 ? 0 : 2 + wg, wg == 2 ? 2 : 3 + wg, sm_raw + (wg == 2 ? SM_CV + (warp & 3) * CV_W : SM_HELP + warp * HELP_W), lane, kacc, ec, k0);
  if (wg == 2) {
    conv_role(p, sm_raw, sb, lane, warp & 3, kacc, ec, k0);
    cluster_arrive();
    cluster_wait();
    return;
  } else {
#pragma unroll
    for (int i = 0; i < 5; i++)
      *reinterpret_cast<float4*>(sm_raw + SM_HELP + warp * HELP_W + (i * 32 + lane) * 16) = make_float4(kacc[i][0], kacc[i][1], kacc[i][2], kacc[i][3]);
    __syncwarp();
    mbar_arrive_local(lane == 0, sb + BAR_KB);
    sts32(sb + SM_GW + tid * 4, gwv);
    bar_sync(1, 256);
    int pend = -1;
    {
      float acc[128];
      g1_pass<0>(acc, m, c, tid, pend);
      publish(tid, warp, pend);
      mbar_wait(sb + BAR_C1, 0);
      g1_pass<1>(acc, m, c, tid, pend);
    }
    float acc[64];
#pragma unroll 1
    for (int i = 0; i < 14; i++) {
      mbar_wait(c.full + 8 * (i & 3), (i >> 2) & 1);
      const uint32_t st = sb + SM_RING + (i & 3) * STAGE + wg * 24576;
      const uint64_t da = mk_desc(st, 16, 1024, 1);
      const uint64_t db = mk_desc(st + 8192, 8192, 1024, 1);
      wg_fence();
#pragma unroll
      for (int k = 0; k < 4; k++) {
        wgmma_n128(acc, da + k * 2, db + k * 128, (i | k) != 0);
      }
      wg_commit();
      if (i == 0) publish(tid, warp, pend);
      if (i > 0) {
        wg_wait<1>();
        release_refill(m, c, tid, 16 + i - 1);
      }
    }
    const int g = lane >> 2;
    const int rl = (warp & 3) * 16 + g;
    const uint32_t gv0 = ldg32_coh(g_gate + c.mt2 * 64 + rl), gv1 = ldg32_coh(g_gate + c.mt2 * 64 + rl + 8);
    wg_wait<0>();
    bar_sync(1, 256);
    const uint32_t xb = sb + SM_RING + (tid & 127) * 4;
#pragma unroll
    for (int i = 0; i < 32; i++) sts32(xb + (wg * 32 + i) * 512, __float_as_uint(wg ? acc[i] : acc[32 + i]));
    bar_sync(1, 256);
    mbar_wait(c.full + 8 * (NIT & 3), (NIT >> 2) & 1);
    const uint32_t stg = sb + SM_RING + 32768 + warp * 2304;
    const int adr = wg * 64 + (lane >> 4) * 8 + (lane & 7);
    const uint32_t ab = sb + SM_RING + (NIT % NST) * STAGE + adr * 128 + ((((warp & 3) * 2 + ((lane >> 3) & 1)) ^ (lane & 7)) << 4);
    const uint32_t g0 = __byte_perm(gv0, 0, 0x1010), h0 = __byte_perm(gv0, 0, 0x3232);
    const uint32_t g1 = __byte_perm(gv1, 0, 0x1010), h1 = __byte_perm(gv1, 0, 0x3232);
#pragma unroll
    for (int j = 0; j < 8; j += 2) {
      uint32_t rr[4], av[4];
      ldsm_x4_t(av[0], av[1], av[2], av[3], ab + j * 1024);
#pragma unroll
      for (int e = 0; e < 2; e++) {
        float v[4];
#pragma unroll
        for (int x = 0; x < 4; x++)
          v[x] = (wg ? acc[32 + (j + e) * 4 + x] : acc[(j + e) * 4 + x]) + __uint_as_float(lds32(xb + ((wg ^ 1) * 32 + (j + e) * 4 + x) * 512));
        rr[e * 2] = badd2(bmul2(g0, av[e * 2]), bmul2(h0, pack_bf16(v[0], v[1])));
        rr[e * 2 + 1] = badd2(bmul2(g1, av[e * 2 + 1]), bmul2(h1, pack_bf16(v[2], v[3])));
      }
      stsm_x4(stg + (lane & 15) * 144 + (j + (lane >> 4)) * 16, rr[0], rr[1], rr[2], rr[3]);
    }
    __syncwarp();
    __nv_bfloat16* op = p.out + (size_t)(c.mt2 * 64 + (warp & 3) * 16 + (lane >> 3)) * D_ + c.nt2 * 128 + wg * 64 + (lane & 7) * 8;
#pragma unroll
    for (int i = 0; i < 4; i++) stg128(op + (size_t)i * 4 * D_, lds128(stg + (i * 4 + (lane >> 3)) * 144 + (lane & 7) * 16));
    if (tid == 0) {
      unsigned old = atomicAdd(g_flags + FL_DONE * 32, 1u);
      if (old == gridDim.x - 1) {
        for (int f = 0; f < FL_N; f++) g_flags[f * 32] = 0u;
      }
    }
    __syncwarp();
    cluster_arrive();
    cluster_wait();
    return;
  }
}

typedef CUresult (*EncFn)(CUtensorMap*, CUtensorMapDataType, cuuint32_t, void*, const cuuint64_t*, const cuuint64_t*, const cuuint32_t*,
                          const cuuint32_t*, CUtensorMapInterleave, CUtensorMapSwizzle, CUtensorMapL2promotion, CUtensorMapFloatOOBfill);

void make_map(EncFn enc, CUtensorMap* tm, const void* p, int rank, const cuuint64_t* dims, const cuuint64_t* strides, const cuuint32_t* box,
              CUtensorMapSwizzle sw) {
  cuuint32_t es[3] = {1, 1, 1};
  enc(tm, CU_TENSOR_MAP_DATA_TYPE_BFLOAT16, rank, const_cast<void*>(p), dims, strides, box, es, CU_TENSOR_MAP_INTERLEAVE_NONE, sw,
      CU_TENSOR_MAP_L2_PROMOTION_L2_256B, CU_TENSOR_MAP_FLOAT_OOB_FILL_NONE);
}

}

extern "C" void kernel_launch(void* const* d_in, const int* in_sizes, int n_in, void* d_out, int out_size) {
  (void)in_sizes; (void)n_in; (void)out_size;
  typedef const __nv_bfloat16* bp;
  Params p;
  p.u = (bp)d_in[0]; p.logAr = (bp)d_in[1]; p.Aim = (bp)d_in[2]; p.Cre = (bp)d_in[3]; p.Cim = (bp)d_in[4]; p.logdt = (bp)d_in[5];
  p.Dsk = (bp)d_in[6]; p.gw = (bp)d_in[11]; p.out = (__nv_bfloat16*)d_out;
  bp wg = (bp)d_in[8], wu = (bp)d_in[9], wd = (bp)d_in[10];
  static EncFn enc = nullptr;
  static void* hptr = nullptr;
  static void* aptr = nullptr;
  if (!enc) {
    void* fn = nullptr;
    cudaDriverEntryPointQueryResult q;
    cudaGetDriverEntryPoint("cuTensorMapEncodeTiled", &fn, cudaEnableDefault, &q);
    enc = (EncFn)fn;
    cudaGetSymbolAddress(&hptr, g_h);
    cudaGetSymbolAddress(&aptr, g_a);
    cudaFuncSetAttribute(fused_kernel, cudaFuncAttributeMaxDynamicSharedMemorySize, SMEM_TOTAL);
  }
  Maps m;
  {
    cuuint64_t dm[2] = {D_, L_}, st[1] = {D_ * 2};
    cuuint32_t bx[2] = {64, 128};
    make_map(enc, &m.x, p.u, 2, dm, st, bx, CU_TENSOR_MAP_SWIZZLE_128B);
  }
  {
    cuuint64_t dm[2] = {F_, D_}, st[1] = {F_ * 2};
    cuuint32_t bx[2] = {64, 64};
    make_map(enc, &m.g2, wg, 2, dm, st, bx, CU_TENSOR_MAP_SWIZZLE_128B);
    make_map(enc, &m.u2, wu, 2, dm, st, bx, CU_TENSOR_MAP_SWIZZLE_128B);
  }
  {
    cuuint64_t dm[3] = {32, D_, F_ / 32}, st[2] = {F_ * 2, 64};
    cuuint32_t b3[3] = {32, 64, 3};
    make_map(enc, &m.g3, wg, 3, dm, st, b3, CU_TENSOR_MAP_SWIZZLE_64B);
    make_map(enc, &m.u3, wu, 3, dm, st, b3, CU_TENSOR_MAP_SWIZZLE_64B);
  }
  {
    cuuint64_t dm[2] = {F_, L_}, st[1] = {F_ * 2};
    cuuint32_t bx[2] = {64, 64};
    make_map(enc, &m.h, hptr, 2, dm, st, bx, CU_TENSOR_MAP_SWIZZLE_128B);
  }
  {
    cuuint64_t dm[2] = {D_, F_}, st[1] = {D_ * 2};
    cuuint32_t bx[2] = {64, 64};
    make_map(enc, &m.wd, wd, 2, dm, st, bx, CU_TENSOR_MAP_SWIZZLE_128B);
  }
  {
    cuuint64_t dm[2] = {L_, D_}, st[1] = {L_ * 2};
    cuuint32_t bx[2] = {64, 128};
    make_map(enc, &m.at, aptr, 2, dm, st, bx, CU_TENSOR_MAP_SWIZZLE_128B);
  }
  fused_kernel<<<128, 384, SMEM_TOTAL, cudaStreamPerThread>>>(m, p);
}
```
